```python
import torch

def _softmax(x, axis=-1):
    return torch.softmax(x, dim=axis)
def _gelu(x):
    return torch.nn.functional.gelu(x, approximate="tanh")
def _silu(x):
    return torch.nn.functional.silu(x)
def _sigmoid(x):
    return torch.sigmoid(x)
def _layernorm(x, axis=-1, eps=1e-5):
    m = x.mean(dim=axis, keepdim=True)
    v = x.var(dim=axis, keepdim=True, unbiased=False)
    return (x - m) / torch.sqrt(v + eps)
def _scatter_add(tgt, idx, src, axis=0):
    return tgt.clone().index_add_(axis, idx, src)
def _segment_sum(src, seg, n):
    out = torch.zeros((n,) + src.shape[1:], dtype=src.dtype)
    return out.index_add_(0, seg, src)
def _pad(x, pw):
    flat = tuple(v for pair in reversed(pw) for v in pair)
    return torch.nn.functional.pad(x, flat)

kernel_name = 'sequential_preLN__gqa_block_cached__mixer_token_mlp__decode'

def setup_inputs():

    _w = (lambda a: (lambda t: t.to(torch.bfloat16) if t.is_floating_point() else t)(torch.as_tensor(a)))
    def _A_setup():
        B, Sq, D = 8, 1, 448
        Hq, Hkv, Sk, Dh = 16, 8, 8192, 256
        assert Hq % Hkv == 0, (Hq, Hkv)
        return {
            "x": _w((lambda *s: torch.randn(*s, dtype=torch.bfloat16) * 0.05)(B, Sq, D)),
            "k_cache": _w((lambda *s: torch.randn(*s, dtype=torch.bfloat16) * 1.6)(B, Hkv, Sk, Dh)),
            "v_cache": _w((lambda *s: torch.randn(*s, dtype=torch.bfloat16) * 0.8)(B, Hkv, Sk, Dh)),
            "wq": _w((lambda *s: torch.randn(*s, dtype=torch.bfloat16) * 1.6)(D, Hq * Dh) * (D ** -0.5)),
            "wo": _w((lambda *s: torch.randn(*s, dtype=torch.bfloat16) * 0.8)(Hq * Dh, D) * ((Hq * Dh) ** -0.5)),
        }
    _A_in = _A_setup()

    def _B_setup():
        B, S, D, F = 8, 1, 448, 1792
        return {
            "x": _w((lambda *s: torch.randn(*s, dtype=torch.bfloat16) * 0.05)(B, S, D)),
            "w1": _w((lambda *s: torch.randn(*s, dtype=torch.bfloat16) * 0.4)(S, F) * (S ** -0.5)),
            "b1": _w((lambda *s: torch.randn(*s, dtype=torch.bfloat16) * 0.4)(F) * 0.02),
            "w2": _w((lambda *s: torch.randn(*s, dtype=torch.bfloat16) * 0.4)(F, S) * (F ** -0.5)),
            "b2": _w((lambda *s: torch.randn(*s, dtype=torch.bfloat16) * 0.4)(S) * 0.02),
        }
    _B_in = _B_setup()

    return {
        "A_x": _A_in["x"],
        "A_k_cache": _A_in["k_cache"],
        "A_v_cache": _A_in["v_cache"],
        "A_wq": _A_in["wq"],
        "A_wo": _A_in["wo"],
        "B_x": _B_in["x"],
        "B_w1": _B_in["w1"],
        "B_b1": _B_in["b1"],
        "B_w2": _B_in["w2"],
        "B_b2": _B_in["b2"],
    }

def reference(A_x, A_k_cache, A_v_cache, A_wq, A_wo, B_x, B_w1, B_b1, B_w2, B_b2):
    def _A_ref(x, k_cache, v_cache, wq, wo):
        B, Sq, D = x.shape
        Hq, Dh = 16, 256
        Hkv = k_cache.shape[1]
        rep = Hq // Hkv
        q = (lambda x, *d: x.permute(*d))((x @ wq).reshape(B, Sq, Hq, Dh), 0, 2, 1, 3)
        k = (lambda x, n, axis: torch.repeat_interleave(x, n, dim=axis))(k_cache, rep, axis=1)
        v = (lambda x, n, axis: torch.repeat_interleave(x, n, dim=axis))(v_cache, rep, axis=1)
        scores = torch.einsum("bhqd,bhkd->bhqk", q, k) * (Dh ** -0.5)
        p = _softmax(scores, axis=-1)
        o = torch.einsum("bhqk,bhkd->bhqd", p, v)
        return (lambda x, *d: x.permute(*d))(o, 0, 2, 1, 3).reshape(B, Sq, Hq * Dh) @ wo

    def _B_ref(x, w1, b1, w2, b2):
        B, S, D = x.shape
        h = _layernorm(x, axis=-1)
        u = torch.einsum("bsd,sf->bdf", h, w1) + b1
        u = _gelu(u)
        y = torch.einsum("bdf,fs->bds", u, w2) + b2
        return (lambda x, *d: x.permute(*d))(y, 0, 2, 1)

    x = A_x
    h = x + _A_ref(_layernorm(x, axis=-1), A_k_cache, A_v_cache, A_wq, A_wo)
    h2 = h + _B_ref(_layernorm(h, axis=-1), B_w1, B_b1, B_w2, B_b2)
    return h2
```

```cpp
#include <cuda_runtime.h>
#include <cuda_bf16.h>
#include <cuda.h>
#include <stdint.h>

namespace {

constexpr int NB = 8, DM = 448, HQ = 16, HKV = 8, SK = 8192, DH = 256, FF = 1792;
constexpr int NCTA = 132;
constexpr int NG = 4;
constexpr int GSZ = NCTA / NG;
constexpr int TILE = 32;
constexpr int TPP = SK / TILE;
constexpr int PPG = NB * HKV / NG;
constexpr int TICKETS = PPG * TPP;
constexpr int HS_BYTES = TILE * DH * 2;
#define NSTAGE 10
constexpr int NS = NSTAGE;
constexpr int NITEM = NS / 2;
#define NCONS 2
constexpr int W = NCONS;
constexpr int MT = 16 / W;
constexpr int NSERV = 128;
constexpr int NTHREADS = 32 + 32 * W + NSERV;
constexpr int EARLY_ITEMS = 2;

constexpr int S2_CTAS = 128;
constexpr int S2_COLS = 56;
constexpr int S3_CTAS = 112;

constexpr int SM_RING = 0;
constexpr int SM_WO = NS * HS_BYTES;
constexpr int SM_WO_BYTES = DH * S2_COLS * 2;
constexpr int SM_MISC = SM_WO + SM_WO_BYTES;
constexpr int SM_MISC_BYTES = 4096;
constexpr int SM_BAR = SM_MISC + SM_MISC_BYTES;
constexpr int SM_TOTAL = SM_BAR + 512 + 1024;

constexpr float kQKScaleLog2 = 0.0625f * 1.4426950408889634f;
constexpr unsigned SPIN_LIMIT = 1u << 26;

__device__ uint32_t g_q[NB * HQ * 128];
__device__ float g_part_o[NB * HKV * GSZ * 2 * DH];
__device__ float2 g_part_ml[NB * HKV * GSZ * 2];
__device__ float g_hpart[NB * HQ * DM];
struct Counters {
    unsigned ticket[NG * 32];
    unsigned q_ready[HKV * 32];
    unsigned pair_done[NB * HKV * 32];
    unsigned batch_done[NB * 32];
    unsigned exit_count[32];
};
__device__ Counters g_cnt;
#define TSTAMP(i) do { } while (0)

__device__ __forceinline__ uint32_t smem_u32(const void* p) { return (uint32_t)__cvta_generic_to_shared(p); }
__device__ __forceinline__ void mbar_init(uint32_t bar, uint32_t cnt) {
    asm volatile("mbarrier.init.shared::cta.b64 [%0], %1;" ::"r"(bar), "r"(cnt) : "memory");
}
__device__ __forceinline__ void mbar_expect_tx(uint32_t bar, uint32_t bytes) {
    asm volatile("mbarrier.arrive.expect_tx.shared::cta.b64 _, [%0], %1;" ::"r"(bar), "r"(bytes) : "memory");
}
__device__ __forceinline__ void mbar_arrive(uint32_t bar) {
    asm volatile("mbarrier.arrive.shared::cta.b64 _, [%0];" ::"r"(bar) : "memory");
}
__device__ __forceinline__ bool mbar_try_wait(uint32_t bar, uint32_t parity) {
    uint32_t ok;
    asm volatile(
        "{\n.reg .pred p;\n"
        "mbarrier.try_wait.parity.shared::cta.b64 p, [%1], %2;\n"
        "selp.u32 %0, 1, 0, p;\n}"
        : "=r"(ok) : "r"(bar), "r"(parity) : "memory");
    return ok != 0;
}
__device__ __forceinline__ void mbar_wait(uint32_t bar, uint32_t parity) {
    unsigned n = 0;
    while (!mbar_try_wait(bar, parity)) {
        if (++n > SPIN_LIMIT) __trap();
    }
}
__device__ __forceinline__ void tma_load_3d(uint32_t dst, const CUtensorMap* tm, int row, uint32_t bar) {
    asm volatile(
        "cp.async.bulk.tensor.3d.shared::cluster.global.mbarrier::complete_tx::bytes [%0], [%1, {%3, %4, %5}], [%2];"
        ::"r"(dst), "l"(tm), "r"(bar), "r"(0), "r"(row), "r"(0) : "memory");
}
__device__ __forceinline__ void ldsm_x4(uint32_t a, uint32_t& r0, uint32_t& r1, uint32_t& r2, uint32_t& r3) {
    asm volatile("ldmatrix.sync.aligned.m8n8.x4.shared.b16 {%0,%1,%2,%3}, [%4];"
                 : "=r"(r0), "=r"(r1), "=r"(r2), "=r"(r3) : "r"(a) : "memory");
}
__device__ __forceinline__ void ldsm_x4_t(uint32_t a, uint32_t& r0, uint32_t& r1, uint32_t& r2, uint32_t& r3) {
    asm volatile("ldmatrix.sync.aligned.m8n8.x4.trans.shared.b16 {%0,%1,%2,%3}, [%4];"
                 : "=r"(r0), "=r"(r1), "=r"(r2), "=r"(r3) : "r"(a) : "memory");
}
__device__ __forceinline__ void mma_bf16(float (&d)[4], uint32_t a0, uint32_t a1, uint32_t a2, uint32_t a3,
                                         uint32_t b0, uint32_t b1) {
    asm volatile(
        "mma.sync.aligned.m16n8k16.row.col.f32.bf16.bf16.f32 {%0,%1,%2,%3}, {%4,%5,%6,%7}, {%8,%9}, {%0,%1,%2,%3};"
        : "+f"(d[0]), "+f"(d[1]), "+f"(d[2]), "+f"(d[3])
        : "r"(a0), "r"(a1), "r"(a2), "r"(a3), "r"(b0), "r"(b1));
}
__device__ __forceinline__ float ex2f(float x) {
    float y;
    asm("ex2.approx.ftz.f32 %0, %1;" : "=f"(y) : "f"(x));
    return y;
}
__device__ __forceinline__ float tanh_fast(float x) {
    float y;
    asm("tanh.approx.f32 %0, %1;" : "=f"(y) : "f"(x));
    return y;
}
__device__ __forceinline__ float bf16r(float x) { return __bfloat162float(__float2bfloat16_rn(x)); }
__device__ __forceinline__ float bf_lo(uint32_t w) { return __uint_as_float(w << 16); }
__device__ __forceinline__ float bf_hi(uint32_t w) { return __uint_as_float(w & 0xffff0000u); }
__device__ __forceinline__ uint32_t pack_bf16(float lo, float hi) {
    uint32_t r;
    asm("cvt.rn.bf16x2.f32 %0, %1, %2;" : "=r"(r) : "f"(hi), "f"(lo));
    return r;
}
__device__ __forceinline__ unsigned ld_acquire(const unsigned* p) {
    unsigned v;
    asm volatile("ld.acquire.gpu.global.u32 %0, [%1];" : "=r"(v) : "l"(p) : "memory");
    return v;
}
__device__ __forceinline__ void red_release(unsigned* p, unsigned v) {
    asm volatile("red.release.gpu.global.add.u32 [%0], %1;" ::"l"(p), "r"(v) : "memory");
}
__device__ __forceinline__ void wait_counter(const unsigned* p, unsigned target) {
    unsigned n = 0;
    while (ld_acquire(p) < target) {
        __nanosleep(32);
        if (++n > SPIN_LIMIT) __trap();
    }
}
__device__ __forceinline__ void serv_sync() { asm volatile("bar.sync 1, 128;" ::: "memory"); }
__device__ __forceinline__ float warp_sum(float v) {
#pragma unroll
    for (int o = 16; o > 0; o >>= 1) v += __shfl_xor_sync(0xffffffffu, v, o);
    return v;
}
__device__ __forceinline__ float serv_sum(float v, float* red, int stid) {
    v = warp_sum(v);
    if ((stid & 31) == 0) red[stid >> 5] = v;
    serv_sync();
    float r = (red[0] + red[1]) + (red[2] + red[3]);
    return r;
}

__global__ void __launch_bounds__(NTHREADS, 1)
fused_decode_kernel(const __grid_constant__ CUtensorMap tmk, const __grid_constant__ CUtensorMap tmv,
                    const __nv_bfloat16* __restrict__ x, const __nv_bfloat16* __restrict__ wq,
                    const __nv_bfloat16* __restrict__ wo, const __nv_bfloat16* __restrict__ w1,
                    const __nv_bfloat16* __restrict__ b1, const __nv_bfloat16* __restrict__ w2,
                    const __nv_bfloat16* __restrict__ b2, __nv_bfloat16* __restrict__ out) {
    extern __shared__ unsigned char smem_raw[];
    const uint32_t sraw = smem_u32(smem_raw);
    const uint32_t sbase = (sraw + 1023u) & ~1023u;
    unsigned char* sptr = smem_raw + (sbase - sraw);
    const uint32_t bar_full = sbase + SM_BAR;
    const uint32_t bar_empty = bar_full + NS * 8;
    const uint32_t bar_wq = bar_empty + NS * 8;
    volatile int* info = reinterpret_cast<volatile int*>(sptr + SM_BAR + 256);

    const int tid = threadIdx.x, warp = tid >> 5, lane = tid & 31;
    const int cta = blockIdx.x;
    const int grp = cta % NG, mem = cta / NG;

    if (tid == 0) {
        TSTAMP(0);
        for (int s = 0; s < NS; s++) {
            mbar_init(bar_full + s * 8, 1);
            mbar_init(bar_empty + s * 8, W);
        }
        mbar_init(bar_wq, NSERV);
        asm volatile("fence.mbarrier_init.release.cluster;" ::: "memory");
        asm volatile("fence.proxy.async;" ::: "memory");
        asm volatile("prefetch.tensormap [%0];" ::"l"(&tmk) : "memory");
        asm volatile("prefetch.tensormap [%0];" ::"l"(&tmv) : "memory");
    }
    __syncthreads();

    if (warp == 0) {
        if (lane == 0) {
            unsigned* tick = &g_cnt.ticket[grp * 32];
            int next = mem;
            int n = 0;
            int slot = 0, ph = 0;
            while (true) {
                const int tk = next;
                if (tk < TICKETS) {
                    if (n + 1 < NITEM) next = mem + (n + 1) * GSZ;
                    else next = NITEM * GSZ + (int)atomicAdd(tick, 1u);
                }
                if (n == EARLY_ITEMS) mbar_wait(bar_wq, 0);
                const uint32_t fk = bar_full + (2 * slot) * 8, fv = fk + 8;
                if (n >= NITEM) mbar_wait(bar_empty + (2 * slot) * 8, ph ^ 1);
                if (tk >= TICKETS) {
                    info[slot] = -1;
                    mbar_arrive(fk);
                    break;
                }
                const int pl = tk / TPP;
                const int pair = pl * NG + grp;
                const int row = pair * SK + (tk - pl * TPP) * TILE;
                info[slot] = pl;
                mbar_expect_tx(fk, HS_BYTES);
                tma_load_3d(sbase + SM_RING + (2 * slot) * HS_BYTES, &tmk, row, fk);
                if (n >= NITEM) mbar_wait(bar_empty + (2 * slot + 1) * 8, ph ^ 1);
                mbar_expect_tx(fv, HS_BYTES);
                tma_load_3d(sbase + SM_RING + (2 * slot + 1) * HS_BYTES, &tmv, row, fv);
                n++;
                if (++slot == NITEM) { slot = 0; ph ^= 1; }
            }
            TSTAMP(1);
        }
    } else if (warp <= W) {
        const int cw = warp - 1;
        const int g = lane >> 2, t = lane & 3;
        const int r8 = lane & 7, mi = lane >> 3;
        const uint32_t koff0 = r8 * 128 + ((mi ^ r8) << 4);
        const uint32_t koff1 = koff0 ^ 64;
        const uint32_t voff = (mi >> 1) * 1024 + r8 * 128 + (((mi & 1) ^ r8) << 4);

        uint32_t qa[32];
        float acc[MT][4];
        float m_run = -3.0e38f, l_run = 0.f;
#pragma unroll
        for (int i = 0; i < MT; i++) { acc[i][0] = acc[i][1] = acc[i][2] = acc[i][3] = 0.f; }
        int cur = -1;
        int slot = 0, ph = 0;
        bool first = true;
        while (true) {
            const uint32_t fk = bar_full + (2 * slot) * 8;
            mbar_wait(fk, ph);
            const int pl = info[slot];
            if (pl != cur) {
                const int upto = (pl < 0) ? PPG : pl;
                if (cur >= 0) {
                    const int pair = cur * NG + grp;
                    float* po = g_part_o + ((size_t)(pair * GSZ + mem) * 2) * DH + cw * (MT * 16);
#pragma unroll
                    for (int i = 0; i < MT; i++) {
                        if ((i & 3) == t) {
                            __stcg(po + i * 16 + g, acc[i][0]);
                            __stcg(po + DH + i * 16 + g, acc[i][1]);
                            __stcg(po + i * 16 + 8 + g, acc[i][2]);
                            __stcg(po + DH + i * 16 + 8 + g, acc[i][3]);
                        }
                    }
                    float l = l_run;
                    l += __shfl_xor_sync(0xffffffffu, l, 1);
                    l += __shfl_xor_sync(0xffffffffu, l, 2);
                    if (cw == 0 && t == 0 && g < 2)
                        __stcg(&g_part_ml[(pair * GSZ + mem) * 2 + g], make_float2(m_run, l));
                    __syncwarp();
                    if (lane == 0) { __threadfence(); red_release(&g_cnt.pair_done[pair * 32], 1u); }
                }
                for (int p = cur + 1; p < upto; p++) {
                    const int pair = p * NG + grp;
                    if (cw == 0 && lane < 2)
                        __stcg(&g_part_ml[(pair * GSZ + mem) * 2 + lane], make_float2(-3.0e38f, 0.f));
                    __syncwarp();
                    if (lane == 0) { __threadfence(); red_release(&g_cnt.pair_done[pair * 32], 1u); }
                }
                if (pl < 0) break;
                cur = pl;
                const int pair = pl * NG + grp;
                const int b = pair >> 3, h = pair & 7;
                if (first || true) {
                    if (lane == 0) wait_counter(&g_cnt.q_ready[h * 32], 16u);
                    __syncwarp();
                    if (first && lane == 0 && cw == 0) TSTAMP(2);
                    first = false;
                }
                const uint4* qp = reinterpret_cast<const uint4*>(g_q + ((b * HQ + 2 * h + (g & 1)) * 4 + t) * 32);
#pragma unroll
                for (int i = 0; i < 8; i++) {
                    uint4 v = __ldcg(qp + i);
                    qa[4 * i] = v.x; qa[4 * i + 1] = v.y; qa[4 * i + 2] = v.z; qa[4 * i + 3] = v.w;
                }
                m_run = -3.0e38f; l_run = 0.f;
#pragma unroll
                for (int i = 0; i < MT; i++) { acc[i][0] = acc[i][1] = acc[i][2] = acc[i][3] = 0.f; }
            }
            const uint32_t kb = sbase + SM_RING + (2 * slot) * HS_BYTES;
            const uint32_t vb = kb + HS_BYTES;
            float s[4][4];
#pragma unroll
            for (int nt = 0; nt < 4; nt++) { s[nt][0] = s[nt][1] = s[nt][2] = s[nt][3] = 0.f; }
#pragma unroll
            for (int jj = 0; jj < 8; jj++) {
#pragma unroll
                for (int nt = 0; nt < 4; nt++) {
                    uint32_t b0, b1r, b2r, b3;
                    ldsm_x4(kb + (jj >> 1) * 4096 + nt * 1024 + ((jj & 1) ? koff1 : koff0), b0, b1r, b2r, b3);
                    mma_bf16(s[nt], qa[4 * jj], 0u, qa[4 * jj + 1], 0u, b0, b1r);
                    mma_bf16(s[nt], qa[4 * jj + 2], 0u, qa[4 * jj + 3], 0u, b2r, b3);
                }
            }
            __syncwarp();
            if (lane == 0) mbar_arrive(bar_empty + (2 * slot) * 8);
            float mx = -3.0e38f;
#pragma unroll
            for (int nt = 0; nt < 4; nt++) {
                s[nt][0] = bf16r(s[nt][0]) * kQKScaleLog2;
                s[nt][1] = bf16r(s[nt][1]) * kQKScaleLog2;
                mx = fmaxf(mx, fmaxf(s[nt][0], s[nt][1]));
            }
            mx = fmaxf(mx, __shfl_xor_sync(0xffffffffu, mx, 1));
            mx = fmaxf(mx, __shfl_xor_sync(0xffffffffu, mx, 2));
            if (__any_sync(0xffffffffu, mx > m_run)) {
                const float m_new = fmaxf(m_run, mx);
                const float f = ex2f(m_run - m_new);
                const float fo = __shfl_xor_sync(0xffffffffu, f, 4);
                const float f0 = (g & 1) ? fo : f, f1 = (g & 1) ? f : fo;
                m_run = m_new;
                l_run *= f;
#pragma unroll
                for (int i = 0; i < MT; i++) {
                    acc[i][0] *= f0; acc[i][1] *= f1; acc[i][2] *= f0; acc[i][3] *= f1;
                }
            }
            uint32_t pb[4];
#pragma unroll
            for (int nt = 0; nt < 4; nt++) {
                const float p0 = ex2f(s[nt][0] - m_run), p1 = ex2f(s[nt][1] - m_run);
                l_run += p0 + p1;
                pb[nt] = pack_bf16(p0, p1);
            }
            mbar_wait(fk + 8, ph);
#pragma unroll
            for (int kk = 0; kk < 2; kk++) {
#pragma unroll
                for (int i = 0; i < MT; i++) {
                    const int mt = cw * MT + i;
                    uint32_t a0, a1, a2, a3;
                    ldsm_x4_t(vb + (mt >> 2) * 4096 + kk * 2048 + (voff ^ ((i & 3) << 5)), a0, a1, a2, a3);
                    mma_bf16(acc[i], a0, a1, a2, a3, pb[2 * kk], pb[2 * kk + 1]);
                }
            }
            __syncwarp();
            if (lane == 0) mbar_arrive(bar_empty + (2 * slot + 1) * 8);
            if (++slot == NITEM) { slot = 0; ph ^= 1; }
        }
        if (lane == 0 && cw == 0) TSTAMP(3);
    } else {
        const int st = tid - 32 * (W + 1);
        const int sw = st >> 5;
        float* xs = reinterpret_cast<float*>(sptr + SM_WO);
        float* misc = reinterpret_cast<float*>(sptr + SM_MISC);

        if (cta < 128) {
            const int cp = st & 15, kg = st >> 4;
            const uint32_t* wqp = reinterpret_cast<const uint32_t*>(wq) + (size_t)(kg * 56) * 2048 + cta * 16 + cp;
            uint32_t wv[56];
#pragma unroll
            for (int r = 0; r < 56; r++) wv[r] = __ldg(wqp + (size_t)r * 2048);
#pragma unroll
            for (int bb = 0; bb < 2; bb++) {
                const int b = 2 * sw + bb;
                float v[14];
                float sum = 0.f;
#pragma unroll
                for (int i = 0; i < 14; i++) { v[i] = __bfloat162float(x[b * DM + i * 32 + lane]); sum += v[i]; }
                const float mean = warp_sum(sum) * (1.f / DM);
                float sq = 0.f;
#pragma unroll
                for (int i = 0; i < 14; i++) { const float d = v[i] - mean; sq += d * d; }
                const float var = warp_sum(sq) * (1.f / DM);
                const float mb = bf16r(mean);
                const float den = bf16r(sqrtf(bf16r(bf16r(var) + 1e-5f)));
#pragma unroll
                for (int i = 0; i < 14; i++) xs[b * DM + i * 32 + lane] = bf16r(bf16r(v[i] - mb) / den);
            }
            serv_sync();
            float qacc[8][2];
#pragma unroll
            for (int b = 0; b < 8; b++) { qacc[b][0] = 0.f; qacc[b][1] = 0.f; }
#pragma unroll
            for (int r4 = 0; r4 < 14; r4++) {
#pragma unroll
                for (int b = 0; b < 8; b++) {
                    const float4 xv = *reinterpret_cast<const float4*>(xs + b * DM + kg * 56 + r4 * 4);
                    qacc[b][0] = fmaf(xv.x, bf_lo(wv[4 * r4]), qacc[b][0]);
                    qacc[b][1] = fmaf(xv.x, bf_hi(wv[4 * r4]), qacc[b][1]);
                    qacc[b][0] = fmaf(xv.y, bf_lo(wv[4 * r4 + 1]), qacc[b][0]);
                    qacc[b][1] = fmaf(xv.y, bf_hi(wv[4 * r4 + 1]), qacc[b][1]);
                    qacc[b][0] = fmaf(xv.z, bf_lo(wv[4 * r4 + 2]), qacc[b][0]);
                    qacc[b][1] = fmaf(xv.z, bf_hi(wv[4 * r4 + 2]), qacc[b][1]);
                    qacc[b][0] = fmaf(xv.w, bf_lo(wv[4 * r4 + 3]), qacc[b][0]);
                    qacc[b][1] = fmaf(xv.w, bf_hi(wv[4 * r4 + 3]), qacc[b][1]);
                }
            }
            mbar_arrive(bar_wq);
#pragma unroll
            for (int b = 0; b < 8; b++) {
                qacc[b][0] += __shfl_xor_sync(0xffffffffu, qacc[b][0], 16);
                qacc[b][1] += __shfl_xor_sync(0xffffffffu, qacc[b][1], 16);
            }
            if (lane < 16) {
#pragma unroll
                for (int b = 0; b < 8; b++)
                    *reinterpret_cast<float2*>(misc + sw * 256 + b * 32 + 2 * cp) = make_float2(qacc[b][0], qacc[b][1]);
            }
            serv_sync();
            {
                const int b = st >> 4, c2 = st & 15;
                float v0 = 0.f, v1 = 0.f;
#pragma unroll
                for (int w_ = 0; w_ < 4; w_++) {
                    const float2 p = *reinterpret_cast<const float2*>(misc + w_ * 256 + b * 32 + 2 * c2);
                    v0 += p.x; v1 += p.y;
                }
                const int qh = cta >> 3;
                const int col = (cta & 7) * 32 + 2 * c2;
                const int c8 = col >> 3, tt = (col & 7) >> 1;
                __stcg(&g_q[((b * HQ + qh) * 4 + tt) * 32 + c8], pack_bf16(v0, v1));
            }
            __threadfence();
            serv_sync();
            if (st == 0) { red_release(&g_cnt.q_ready[(cta >> 4) * 32], 1u); TSTAMP(4); }
        } else {
            mbar_arrive(bar_wq);
        }

        const int s2_i = cta >> 3, s2_j = cta & 7;
        if (cta < S2_CTAS) {
            const uint4* src = reinterpret_cast<const uint4*>(wo + (size_t)(s2_i * DH) * DM + s2_j * S2_COLS);
            uint4* dst = reinterpret_cast<uint4*>(sptr + SM_WO);
            uint4 tmp[14];
#pragma unroll
            for (int k = 0; k < 14; k++) {
                const int c = st + k * 128;
                const int r = c / 7, cc = c - r * 7;
                tmp[k] = __ldg(src + (size_t)r * (DM / 8) + cc);
            }
#pragma unroll
            for (int k = 0; k < 14; k++) dst[st + k * 128] = tmp[k];
        }
        float pw1[14], pb1[14], pw2[14];
        float xrow_dummy = 0.f; (void)xrow_dummy;
        if (cta < S3_CTAS) {
#pragma unroll
            for (int k = 0; k < 7; k++) {
                const int f2 = st + k * 128;
                const uint32_t a = __ldg(reinterpret_cast<const uint32_t*>(w1) + f2);
                const uint32_t bq = __ldg(reinterpret_cast<const uint32_t*>(b1) + f2);
                const uint32_t c = __ldg(reinterpret_cast<const uint32_t*>(w2) + f2);
                pw1[2 * k] = bf_lo(a); pw1[2 * k + 1] = bf_hi(a);
                pb1[2 * k] = bf_lo(bq); pb1[2 * k + 1] = bf_hi(bq);
                pw2[2 * k] = bf_lo(c); pw2[2 * k + 1] = bf_hi(c);
            }
        } else {
#pragma unroll
            for (int k = 0; k < 14; k++) { pw1[k] = 0.f; pb1[k] = 0.f; pw2[k] = 0.f; }
        }
        const float b2v = __bfloat162float(b2[0]);
        serv_sync();

        float* o_s = misc;
        float* kred = misc + 256;
        float* red = misc + 512;
        float* tv = misc + 576;
        unsigned exit_old = 0;
        for (int b = 0; b < NB; b++) {
            if (cta < S2_CTAS) {
                const int pair = b * HKV + (s2_i >> 1), hh = s2_i & 1;
                if (st == 0) wait_counter(&g_cnt.pair_done[pair * 32], (unsigned)(GSZ * W));
                serv_sync();
                if (b == NB - 1 && st == 0) TSTAMP(5);
                const float2* mlp = g_part_ml + (pair * GSZ) * 2 + hh;
                const float2* op = reinterpret_cast<const float2*>(g_part_o + ((size_t)(pair * GSZ) * 2 + hh) * DH) + st;
                static_assert(GSZ == 33, "combine assumes 32 + 1 slots");
                float2 ov[GSZ];
                const float2 mla = __ldcg(mlp + lane * 2);
                const float2 mlb = __ldcg(mlp + 32 * 2);
#pragma unroll
                for (int s = 0; s < GSZ; s++) ov[s] = __ldcg(op + s * DH);
                float M = mla.x;
#pragma unroll
                for (int o = 16; o > 0; o >>= 1) M = fmaxf(M, __shfl_xor_sync(0xffffffffu, M, o));
                M = fmaxf(M, mlb.x);
                const float wa_ = (mla.y > 0.f) ? ex2f(mla.x - M) : 0.f;
                const float wb_ = (mlb.y > 0.f) ? ex2f(mlb.x - M) : 0.f;
                const float L = warp_sum(wa_ * mla.y) + wb_ * mlb.y;
                float o0 = 0.f, o1 = 0.f;
#pragma unroll
                for (int s = 0; s < GSZ; s++) {
                    const float w_ = (s < 32) ? __shfl_sync(0xffffffffu, wa_, s & 31) : wb_;
                    if (w_ > 0.f) {
                        o0 = fmaf(w_, ov[s].x, o0);
                        o1 = fmaf(w_, ov[s].y, o1);
                    }
                }
                const float inv = 1.f / L;
                *reinterpret_cast<float2*>(o_s + 2 * st) = make_float2(bf16r(o0 * inv), bf16r(o1 * inv));
                serv_sync();
                if (st < 112) {
                    const int kq = st / 28, cp = st - kq * 28;
                    const uint32_t* wp = reinterpret_cast<const uint32_t*>(sptr + SM_WO) + (kq * 64) * 28 + cp;
                    const float* ob = o_s + kq * 64;
                    float a0 = 0.f, a1 = 0.f, c0 = 0.f, c1 = 0.f;
#pragma unroll 8
                    for (int d = 0; d < 64; d += 2) {
                        const uint32_t wa = wp[d * 28], wb = wp[(d + 1) * 28];
                        const float2 oo = *reinterpret_cast<const float2*>(ob + d);
                        a0 = fmaf(oo.x, bf_lo(wa), a0); a1 = fmaf(oo.x, bf_hi(wa), a1);
                        c0 = fmaf(oo.y, bf_lo(wb), c0); c1 = fmaf(oo.y, bf_hi(wb), c1);
                    }
                    *reinterpret_cast<float2*>(kred + kq * 56 + 2 * cp) = make_float2(a0 + c0, a1 + c1);
                }
                serv_sync();
                if (st < 56) {
                    const float v = (kred[st] + kred[56 + st]) + (kred[112 + st] + kred[168 + st]);
                    __stcg(&g_hpart[(b * HQ + s2_i) * DM + s2_j * S2_COLS + st], v);
                    __threadfence();
                }
                serv_sync();
                if (st == 0) red_release(&g_cnt.batch_done[b * 32], 1u);
                if (b == NB - 1 && st == 0) TSTAMP(6);
            }
            if (cta < S3_CTAS) {
                if (st == 0) {
                    wait_counter(&g_cnt.batch_done[b * 32], (unsigned)S2_CTAS);
                    if (b == NB - 1) exit_old = atomicAdd(&g_cnt.exit_count[0], 1u);
                }
                serv_sync();
                if (b == NB - 1 && st == 0) TSTAMP(7);
                float hv[4] = {0.f, 0.f, 0.f, 0.f};
                if (st < 112) {
                    const float4* hp = reinterpret_cast<const float4*>(g_hpart + (size_t)b * HQ * DM) + st;
                    float4 pv[16];
#pragma unroll
                    for (int i = 0; i < 16; i++) pv[i] = __ldcg(hp + i * (DM / 4));
                    const uint2 xw = __ldg(reinterpret_cast<const uint2*>(x + b * DM) + st);
                    float a0 = 0.f, a1 = 0.f, a2 = 0.f, a3 = 0.f;
#pragma unroll
                    for (int i = 0; i < 16; i++) { a0 += pv[i].x; a1 += pv[i].y; a2 += pv[i].z; a3 += pv[i].w; }
                    hv[0] = bf16r(bf_lo(xw.x) + bf16r(a0));
                    hv[1] = bf16r(bf_hi(xw.x) + bf16r(a1));
                    hv[2] = bf16r(bf_lo(xw.y) + bf16r(a2));
                    hv[3] = bf16r(bf_hi(xw.y) + bf16r(a3));
                }
                float yv[4] = {hv[0], hv[1], hv[2], hv[3]};
#pragma unroll
                for (int pass = 0; pass < 2; pass++) {
                    const float mean = serv_sum((yv[0] + yv[1]) + (yv[2] + yv[3]), red + pass * 8, st) * (1.f / DM);
                    float sq = 0.f;
                    if (st < 112) {
#pragma unroll
                        for (int k = 0; k < 4; k++) { const float d = yv[k] - mean; sq += d * d; }
                    }
                    const float var = serv_sum(sq, red + pass * 8 + 4, st) * (1.f / DM);
                    const float mb = bf16r(mean);
                    const float den = bf16r(sqrtf(bf16r(bf16r(var) + 1e-5f)));
                    if (st < 112) {
#pragma unroll
                        for (int k = 0; k < 4; k++) yv[k] = bf16r(bf16r(yv[k] - mb) / den);
                    }
                }
                if (st == cta) {
                    *reinterpret_cast<float4*>(tv) = make_float4(yv[0], yv[1], yv[2], yv[3]);
                    *reinterpret_cast<float4*>(tv + 4) = make_float4(hv[0], hv[1], hv[2], hv[3]);
                }
                serv_sync();
                const float4 t4 = *reinterpret_cast<const float4*>(tv);
                const float tt[4] = {t4.x, t4.y, t4.z, t4.w};
                float ya[4] = {0.f, 0.f, 0.f, 0.f};
#pragma unroll
                for (int k = 0; k < 14; k++) {
#pragma unroll
                    for (int c = 0; c < 4; c++) {
                        const float u = fmaf(tt[c], pw1[k], pb1[k]);
                        const float z = u * fmaf(u * u, 0.7978845608028654f * 0.044715f, 0.7978845608028654f);
                        const float hu = 0.5f * u;
                        const float gl = fmaf(hu, tanh_fast(z), hu);
                        ya[c] = fmaf(gl, pw2[k], ya[c]);
                    }
                }
#pragma unroll
                for (int c = 0; c < 4; c++) ya[c] = warp_sum(ya[c]);
                if (lane == 0) *reinterpret_cast<float4*>(red + 16 + sw * 4) = make_float4(ya[0], ya[1], ya[2], ya[3]);
                serv_sync();
                if (st < 4) {
                    const float y = (red[16 + st] + red[20 + st]) + (red[24 + st] + red[28 + st]);
                    const float y2 = bf16r(bf16r(y) + b2v);
                    out[b * DM + cta * 4 + st] = __float2bfloat16_rn(tv[4 + st] + y2);
                }
                serv_sync();
            }
        }
        if (st == 0) {
            TSTAMP(8);
            if (cta >= S3_CTAS) exit_old = 0xffffffffu;
        }
        if (st == 0) misc[600] = __uint_as_float(exit_old);
    }
    __syncthreads();
    if (tid == 0) {
        float* misc = reinterpret_cast<float*>(sptr + SM_MISC);
        unsigned old = __float_as_uint(misc[600]);
        if (cta >= S3_CTAS) old = atomicAdd(&g_cnt.exit_count[0], 1u);
        if (old == NCTA - 1) {
            for (int i = 0; i < NG; i++) g_cnt.ticket[i * 32] = 0;
            for (int i = 0; i < HKV; i++) g_cnt.q_ready[i * 32] = 0;
            for (int i = 0; i < NB * HKV; i++) g_cnt.pair_done[i * 32] = 0;
            for (int i = 0; i < NB; i++) g_cnt.batch_done[i * 32] = 0;
            g_cnt.exit_count[0] = 0;
        }
        TSTAMP(9);
    }
}

typedef CUresult (*EncodeTiledFn)(CUtensorMap*, CUtensorMapDataType, cuuint32_t, void*, const cuuint64_t*,
                                  const cuuint64_t*, const cuuint32_t*, const cuuint32_t*, CUtensorMapInterleave,
                                  CUtensorMapSwizzle, CUtensorMapL2promotion, CUtensorMapFloatOOBfill);

}

extern "C" void kernel_launch(void* const* d_in, const int* in_sizes, int n_in, void* d_out, int out_size) {
    (void)in_sizes; (void)n_in; (void)out_size;
    const __nv_bfloat16* x = (const __nv_bfloat16*)d_in[0];
    const __nv_bfloat16* wq = (const __nv_bfloat16*)d_in[3];
    const __nv_bfloat16* wo = (const __nv_bfloat16*)d_in[4];
    const __nv_bfloat16* w1 = (const __nv_bfloat16*)d_in[6];
    const __nv_bfloat16* b1 = (const __nv_bfloat16*)d_in[7];
    const __nv_bfloat16* w2 = (const __nv_bfloat16*)d_in[8];
    const __nv_bfloat16* b2 = (const __nv_bfloat16*)d_in[9];

    static EncodeTiledFn enc = nullptr;
    if (!enc) {
        void* fn = nullptr;
        cudaDriverEntryPointQueryResult qr;
        cudaGetDriverEntryPoint("cuTensorMapEncodeTiled", &fn, cudaEnableDefault, &qr);
        enc = (EncodeTiledFn)fn;
        cudaFuncSetAttribute(fused_decode_kernel, cudaFuncAttributeMaxDynamicSharedMemorySize, SM_TOTAL);
    }
    CUtensorMap tmk, tmv;
    const cuuint64_t gd[3] = {64, (cuuint64_t)NB * HKV * SK, 4};
    const cuuint64_t gs[2] = {512, 128};
    const cuuint32_t bd[3] = {64, TILE, 4};
    const cuuint32_t es[3] = {1, 1, 1};
    enc(&tmk, CU_TENSOR_MAP_DATA_TYPE_BFLOAT16, 3, d_in[1], gd, gs, bd, es, CU_TENSOR_MAP_INTERLEAVE_NONE,
        CU_TENSOR_MAP_SWIZZLE_128B, CU_TENSOR_MAP_L2_PROMOTION_L2_256B, CU_TENSOR_MAP_FLOAT_OOB_FILL_NONE);
    enc(&tmv, CU_TENSOR_MAP_DATA_TYPE_BFLOAT16, 3, d_in[2], gd, gs, bd, es, CU_TENSOR_MAP_INTERLEAVE_NONE,
        CU_TENSOR_MAP_SWIZZLE_128B, CU_TENSOR_MAP_L2_PROMOTION_L2_256B, CU_TENSOR_MAP_FLOAT_OOB_FILL_NONE);
    fused_decode_kernel<<<NCTA, NTHREADS, SM_TOTAL>>>(tmk, tmv, x, wq, wo, w1, b1, w2, b2, (__nv_bfloat16*)d_out);
}
```

```cpp
#include <cuda_runtime.h>
#include <cuda_bf16.h>
#include <cuda.h>
#include <stdint.h>

namespace {

constexpr int NB = 8, DM = 448, HQ = 16, HKV = 8, SK = 8192, DH = 256;
constexpr int NCTA = 132;
constexpr int NG = 4;
constexpr int GSZ = NCTA / NG;
constexpr int TILE = 32;
constexpr int TPP = SK / TILE;
constexpr int PPG = NB * HKV / NG;
constexpr int TICKETS = PPG * TPP;
constexpr int HS_BYTES = TILE * DH * 2;
#define NSTAGE 10
constexpr int NS = NSTAGE;
constexpr int NITEM = NS / 2;
#define NCONS 4
constexpr int W = NCONS;
constexpr int MT = 16 / W;
constexpr int NSERV = 128;
constexpr int NTHREADS = 32 + 32 * W + NSERV;
#define EARLYN 2
constexpr int EARLY_ITEMS = EARLYN;
static_assert(EARLY_ITEMS <= NITEM - 1, "wq staging uses the last ring slot");

#define ROTN 64
constexpr int ROT = ROTN;
#define PACE 100
constexpr int S2_CTAS = 128;
constexpr int S2_COLS = 56;
constexpr int S3_CTAS = 112;

constexpr int SM_RING = 0;
constexpr int SM_WQ = (NS - 2) * HS_BYTES;
constexpr int SM_WO = NS * HS_BYTES;
constexpr int SM_WO_BYTES = DH * S2_COLS * 2;
constexpr int SM_MISC = SM_WO + SM_WO_BYTES;
constexpr int SM_MISC_BYTES = 4096 + NB * DM * 2;
constexpr int SM_QS = SM_MISC + SM_MISC_BYTES;
constexpr int SM_QS_BYTES = PPG * 2 * DH * 2;
constexpr int SM_BAR = SM_QS + SM_QS_BYTES;
constexpr int SM_TOTAL = SM_BAR + 512 + 1024;
constexpr int XS_PITCH = DM + 8;

constexpr float kQKScaleLog2 = 0.0625f * 1.4426950408889634f;
constexpr float kNegBig = -3.0e38f;
constexpr unsigned SPIN_LIMIT = 1u << 24;

__device__ __align__(128) uint32_t g_q[NB * HQ * DH];
__device__ __align__(128) uint32_t g_po[NB * HKV * GSZ * 2 * DH];
__device__ __align__(128) uint32_t g_pml[NB * HKV * 2 * GSZ * 8];
__device__ __align__(128) uint32_t g_hp[NB * HQ * DM];
struct __align__(128) Counters {
    unsigned ticket[32];
    unsigned hint_q[HKV * 32];
    unsigned hint_pair[NB * HKV * 32];
    unsigned hint_batch[NB * 32];
    unsigned epoch[32];
};
__device__ Counters g_cnt;
#define TSTAMP(i) do { } while (0)

__device__ __forceinline__ uint32_t smem_u32(const void* p) { return (uint32_t)__cvta_generic_to_shared(p); }
__device__ __forceinline__ void mbar_init(uint32_t bar, uint32_t cnt) {
    asm volatile("mbarrier.init.shared::cta.b64 [%0], %1;" ::"r"(bar), "r"(cnt) : "memory");
}
__device__ __forceinline__ void mbar_expect_tx(uint32_t bar, uint32_t bytes) {
    asm volatile("mbarrier.arrive.expect_tx.shared::cta.b64 _, [%0], %1;" ::"r"(bar), "r"(bytes) : "memory");
}
__device__ __forceinline__ void mbar_arrive(uint32_t bar) {
    asm volatile("mbarrier.arrive.shared::cta.b64 _, [%0];" ::"r"(bar) : "memory");
}
__device__ __forceinline__ bool mbar_try_wait(uint32_t bar, uint32_t parity) {
    uint32_t ok;
    asm volatile(
        "{\n.reg .pred p;\n"
        "mbarrier.try_wait.parity.shared::cta.b64 p, [%1], %2;\n"
        "selp.u32 %0, 1, 0, p;\n}"
        : "=r"(ok) : "r"(bar), "r"(parity) : "memory");
    return ok != 0;
}
__device__ __forceinline__ void mbar_wait(uint32_t bar, uint32_t parity) {
    unsigned n = 0;
    while (!mbar_try_wait(bar, parity)) {
        if (++n > SPIN_LIMIT) __trap();
    }
}
__device__ __forceinline__ void tma_load_3d(uint32_t dst, const CUtensorMap* tm, int row, uint32_t bar, uint64_t pol) {
    asm volatile(
        "cp.async.bulk.tensor.3d.shared::cluster.global.mbarrier::complete_tx::bytes.L2::cache_hint [%0], [%1, {%3, %4, %5}], [%2], %6;"
        ::"r"(dst), "l"(tm), "r"(bar), "r"(0), "r"(row), "r"(0), "l"(pol) : "memory");
}
__device__ __forceinline__ void cp_async16(uint32_t dst, const void* src) {
    asm volatile("cp.async.cg.shared.global [%0], [%1], 16;" ::"r"(dst), "l"(src) : "memory");
}
__device__ __forceinline__ void cp_async_wait_all() { asm volatile("cp.async.wait_all;" ::: "memory"); }
__device__ __forceinline__ void ldsm_x4(uint32_t a, uint32_t& r0, uint32_t& r1, uint32_t& r2, uint32_t& r3) {
    asm volatile("ldmatrix.sync.aligned.m8n8.x4.shared.b16 {%0,%1,%2,%3}, [%4];"
                 : "=r"(r0), "=r"(r1), "=r"(r2), "=r"(r3) : "r"(a) : "memory");
}
__device__ __forceinline__ void ldsm_x4_t(uint32_t a, uint32_t& r0, uint32_t& r1, uint32_t& r2, uint32_t& r3) {
    asm volatile("ldmatrix.sync.aligned.m8n8.x4.trans.shared.b16 {%0,%1,%2,%3}, [%4];"
                 : "=r"(r0), "=r"(r1), "=r"(r2), "=r"(r3) : "r"(a) : "memory");
}
__device__ __forceinline__ void mma_bf16(float (&d)[4], uint32_t a0, uint32_t a1, uint32_t a2, uint32_t a3,
                                         uint32_t b0, uint32_t b1) {
    asm(
        "mma.sync.aligned.m16n8k16.row.col.f32.bf16.bf16.f32 {%0,%1,%2,%3}, {%4,%5,%6,%7}, {%8,%9}, {%0,%1,%2,%3};"
        : "+f"(d[0]), "+f"(d[1]), "+f"(d[2]), "+f"(d[3])
        : "r"(a0), "r"(a1), "r"(a2), "r"(a3), "r"(b0), "r"(b1));
}
__device__ __forceinline__ float ex2f(float x) {
    float y;
    asm("ex2.approx.ftz.f32 %0, %1;" : "=f"(y) : "f"(x));
    return y;
}
__device__ __forceinline__ float tanh_fast(float x) {
    float y;
    asm("tanh.approx.f32 %0, %1;" : "=f"(y) : "f"(x));
    return y;
}
__device__ __forceinline__ float bf_lo(uint32_t w) { return __uint_as_float(w << 16); }
__device__ __forceinline__ float bf_hi(uint32_t w) { return __uint_as_float(w & 0xffff0000u); }
__device__ __forceinline__ uint32_t pack_bf16(float lo, float hi) {
    uint32_t r;
    asm("cvt.rn.bf16x2.f32 %0, %1, %2;" : "=r"(r) : "f"(hi), "f"(lo));
    return r;
}
__device__ __forceinline__ float bf16r(float x) { return __uint_as_float(pack_bf16(0.f, x)); }
__device__ __forceinline__ void bf16r2(float& a, float& b) {
    const uint32_t w = pack_bf16(a, b);
    a = bf_lo(w); b = bf_hi(w);
}
__device__ __forceinline__ float warp_max(float v) {
    int i = __float_as_int(v);
    i ^= (i >> 31) & 0x7fffffff;
    i = __reduce_max_sync(0xffffffffu, i);
    i ^= (i >> 31) & 0x7fffffff;
    return __int_as_float(i);
}
__device__ __forceinline__ float sqrt_fast(float x) { float y; asm("sqrt.approx.f32 %0, %1;" : "=f"(y) : "f"(x)); return y; }
__device__ __forceinline__ float rcp_fast(float x) { float y; asm("rcp.approx.f32 %0, %1;" : "=f"(y) : "f"(x)); return y; }
__device__ __forceinline__ uint32_t ldr1(const uint32_t* p) {
    uint32_t v;
    asm volatile("ld.relaxed.gpu.global.u32 %0, [%1];" : "=r"(v) : "l"(p) : "memory");
    return v;
}
__device__ __forceinline__ uint2 ldr2(const uint32_t* p) {
    uint2 v;
    asm volatile("ld.relaxed.gpu.global.v2.u32 {%0,%1}, [%2];" : "=r"(v.x), "=r"(v.y) : "l"(p) : "memory");
    return v;
}
__device__ __forceinline__ uint4 ldr4(const uint32_t* p) {
    uint4 v;
    asm volatile("ld.relaxed.gpu.global.v4.u32 {%0,%1,%2,%3}, [%4];"
                 : "=r"(v.x), "=r"(v.y), "=r"(v.z), "=r"(v.w) : "l"(p) : "memory");
    return v;
}
__device__ __forceinline__ void str1(uint32_t* p, uint32_t v) {
    asm volatile("st.relaxed.gpu.global.u32 [%0], %1;" ::"l"(p), "r"(v) : "memory");
}
__device__ __forceinline__ void str2(uint32_t* p, uint32_t a, uint32_t b) {
    asm volatile("st.relaxed.gpu.global.v2.u32 [%0], {%1,%2};" ::"l"(p), "r"(a), "r"(b) : "memory");
}
__device__ __forceinline__ void str4(uint32_t* p, uint32_t a, uint32_t b, uint32_t c, uint32_t d) {
    asm volatile("st.relaxed.gpu.global.v4.u32 [%0], {%1,%2,%3,%4};" ::"l"(p), "r"(a), "r"(b), "r"(c), "r"(d) : "memory");
}
__device__ __forceinline__ uint32_t enc(float v, uint32_t tag) { return (__float_as_uint(v) & ~1u) | tag; }
__device__ __forceinline__ float dec(uint32_t w) { return __uint_as_float(w & ~1u); }
__device__ __forceinline__ void ldr2_if(uint2& v, const uint32_t* p, uint32_t cond) {
    asm volatile("{\n.reg .pred p;\nsetp.ne.u32 p, %3, 0;\n@p ld.relaxed.gpu.global.v2.u32 {%0,%1}, [%2];\n}"
                 : "+r"(v.x), "+r"(v.y) : "l"(p), "r"(cond) : "memory");
}
__device__ __forceinline__ void ldr4_if(uint4& v, const uint32_t* p, uint32_t cond) {
    asm volatile("{\n.reg .pred p;\nsetp.ne.u32 p, %5, 0;\n@p ld.relaxed.gpu.global.v4.u32 {%0,%1,%2,%3}, [%4];\n}"
                 : "+r"(v.x), "+r"(v.y), "+r"(v.z), "+r"(v.w) : "l"(p), "r"(cond) : "memory");
}
__device__ __forceinline__ void red_add(unsigned* p, unsigned v) {
    asm volatile("red.relaxed.gpu.global.add.u32 [%0], %1;" ::"l"(p), "r"(v) : "memory");
}
__device__ __forceinline__ void wait_hint(const unsigned* p, unsigned target, unsigned ns) {
    unsigned spins = 0;
    while (ldr1(p) < target) {
        __nanosleep(ns);
        if (++spins > SPIN_LIMIT) __trap();
    }
}
__device__ __forceinline__ unsigned atom_add(unsigned* p, unsigned v) {
    unsigned r;
    asm volatile("atom.relaxed.gpu.global.add.u32 %0, [%1], %2;" : "=r"(r) : "l"(p), "r"(v) : "memory");
    return r;
}
__device__ __forceinline__ uint32_t never(float x) { return (__float_as_uint(x) == 0x7fc12345u) ? 8u : 0u; }
__device__ __forceinline__ void serv_sync() { asm volatile("bar.sync 1, 128;" ::: "memory"); }
__device__ __forceinline__ float warp_sum(float v) {
#pragma unroll
    for (int o = 16; o > 0; o >>= 1) v += __shfl_xor_sync(0xffffffffu, v, o);
    return v;
}
__device__ __forceinline__ void warp_layernorm14(float (&v)[14]) {
    const float c = __shfl_sync(0xffffffffu, v[0], 0);
    float s1 = 0.f, s2 = 0.f;
#pragma unroll
    for (int i = 0; i < 14; i++) { const float d = v[i] - c; s1 += d; s2 = fmaf(d, d, s2); }
#pragma unroll
    for (int o = 16; o > 0; o >>= 1) {
        s1 += __shfl_xor_sync(0xffffffffu, s1, o);
        s2 += __shfl_xor_sync(0xffffffffu, s2, o);
    }
    const float dm = s1 * (1.f / DM);
    const float var = fmaxf(fmaf(-dm, dm, s2 * (1.f / DM)), 0.f);
    const float mb = bf16r(c + dm);
    const float rden = rcp_fast(bf16r(sqrt_fast(bf16r(bf16r(var) + 1e-5f))));
#pragma unroll
    for (int i = 0; i < 14; i += 2) {
        float a = v[i] - mb, b = v[i + 1] - mb;
        bf16r2(a, b);
        a *= rden; b *= rden;
        bf16r2(a, b);
        v[i] = a; v[i + 1] = b;
    }
}

__global__ void __launch_bounds__(NTHREADS, 1)
fused_decode_kernel(const __grid_constant__ CUtensorMap tmk, const __grid_constant__ CUtensorMap tmv,
                    const __nv_bfloat16* __restrict__ x, const __nv_bfloat16* __restrict__ wq,
                    const __nv_bfloat16* __restrict__ wo, const __nv_bfloat16* __restrict__ w1,
                    const __nv_bfloat16* __restrict__ b1, const __nv_bfloat16* __restrict__ w2,
                    const __nv_bfloat16* __restrict__ b2, __nv_bfloat16* __restrict__ out) {
    extern __shared__ unsigned char smem_raw[];
    const uint32_t sraw = smem_u32(smem_raw);
    const uint32_t sbase = (sraw + 1023u) & ~1023u;
    unsigned char* sptr = smem_raw + (sbase - sraw);
    const uint32_t bar_full = sbase + SM_BAR;
    const uint32_t bar_empty = bar_full + NS * 8;
    const uint32_t bar_wq = bar_empty + NS * 8;
    const uint32_t bar_qs = bar_wq + 8;
    volatile int* info = reinterpret_cast<volatile int*>(sptr + SM_BAR + 256);
    volatile int* flushed = reinterpret_cast<volatile int*>(sptr + SM_BAR + 320);

    const int tid = threadIdx.x, warp = tid >> 5, lane = tid & 31;
    const int cta = blockIdx.x;
    const int grp = cta % NG, mem = cta / NG;

    if (tid == 0) {
        TSTAMP(0);
        for (int s = 0; s < NS; s++) {
            mbar_init(bar_full + s * 8, 1);
            mbar_init(bar_empty + s * 8, W);
        }
        mbar_init(bar_wq, NSERV);
        mbar_init(bar_qs, W);
        *flushed = 0;
        asm volatile("fence.mbarrier_init.release.cluster;" ::: "memory");
        asm volatile("fence.proxy.async.shared::cta;" ::: "memory");
    }
    float xv[2][14];
    unsigned epoch = 0;
    if (warp > W && cta < 128) {
        const int st = tid - 32 * (W + 1);
#pragma unroll
        for (int k = 0; k < 14; k++) {
            const int c = st + k * 128;
            const int r = c >> 2, cc = c & 3;
            cp_async16(sbase + SM_WQ + r * 64 + ((cc ^ ((r >> 1) & 3)) << 4), wq + (size_t)r * (HQ * DH) + cta * 32 + cc * 8);
        }
        asm volatile("bar.arrive 4, %0;" ::"n"(NSERV + 32) : "memory");
        const unsigned short* xr = reinterpret_cast<const unsigned short*>(x) + (2 * (st >> 5)) * DM + lane;
#pragma unroll
        for (int bb = 0; bb < 2; bb++) {
#pragma unroll
            for (int i = 0; i < 14; i++) {
                unsigned short u;
                asm volatile("ld.global.nc.u16 %0, [%1];" : "=h"(u) : "l"(xr + bb * DM + i * 32));
                xv[bb][i] = __uint_as_float((uint32_t)u << 16);
            }
        }
    }
    if (warp != 0) {
        epoch = ldr1(&g_cnt.epoch[0]);
        asm volatile("bar.sync 3, %0;" ::"n"(NTHREADS) : "memory");
    }

    if (warp == 0) {
        __syncwarp();
        asm volatile("bar.arrive 3, %0;" ::"n"(NTHREADS) : "memory");
        if (cta < 128) asm volatile("bar.sync 4, %0;" ::"n"(NSERV + 32) : "memory");
        if (lane == 0) {
            unsigned* tick = &g_cnt.ticket[grp];
            uint64_t pol;
            asm volatile("createpolicy.fractional.L2::evict_first.b64 %0, 1.0;" : "=l"(pol));
            int next = mem, next2 = mem + GSZ;
            int n = 0;
            uint4 prog = make_uint4(0u, 0u, 0u, 0u);
            int slot = 0, ph = 0;
            while (true) {
                const int tk = next;
                next = next2;
                if (tk < TICKETS) {
                    if (n + 2 < NITEM) next2 = mem + (n + 2) * GSZ;
                    else next2 = NITEM * GSZ + (int)atom_add(tick, 1u);
                }
                if (tk < TICKETS) {
                    unsigned spins = 0;
                    while (tk - NITEM * GSZ > (int)min(min(prog.x, prog.y), min(prog.z, prog.w)) + PACE) {
                        __nanosleep(100);
                        prog = ldr4(g_cnt.ticket);
                        if (++spins > SPIN_LIMIT) __trap();
                    }
                    prog = ldr4(g_cnt.ticket);
                }
                if (n == EARLY_ITEMS) mbar_wait(bar_wq, 0);
                const uint32_t fk = bar_full + (2 * slot) * 8, fv = fk + 8;
                if (n >= NITEM) mbar_wait(bar_empty + (2 * slot) * 8, ph ^ 1);
                if (tk >= TICKETS) {
                    info[slot] = (next < 0) ? -2 : -1;
                    mbar_arrive(fk);
                    break;
                }
                const int pl = tk / TPP;
                const int pair = pl * NG + grp;
                const int row = pair * SK + ((tk - pl * TPP + grp * ROT) & (TPP - 1)) * TILE;
                info[slot] = pl;
                mbar_expect_tx(fk, HS_BYTES);
                tma_load_3d(sbase + SM_RING + (2 * slot) * HS_BYTES, &tmk, row, fk, pol);
                if (n >= NITEM) mbar_wait(bar_empty + (2 * slot + 1) * 8, ph ^ 1);
                mbar_expect_tx(fv, HS_BYTES);
                tma_load_3d(sbase + SM_RING + (2 * slot + 1) * HS_BYTES, &tmv, row, fv, pol);
                n++;
                if (++slot == NITEM) { slot = 0; ph ^= 1; }
            }
            TSTAMP(1);
        }
    } else if (warp <= W) {
        const int cw = warp - 1;
        const int g = lane >> 2, t = lane & 3;
        const int r8 = lane & 7, mi = lane >> 3;
        const int krow = (mi & 1) ? 8 + ((r8 + 4) & 7) : r8;
        const uint32_t koff = krow * 128 + (((mi >> 1) ^ (krow & 7)) << 4);
        const int vi = (r8 >> 1) + 4 * (mi >> 1);
        const int vrow = (r8 & 1) ? 8 + ((vi + 4) & 7) : vi;
        const uint32_t voff = vrow * 128 + (((mi & 1) ^ (vrow & 7)) << 4);
        const int psrc = 4 * t + (g & 1);
        const uint32_t tag = (epoch + 1u) & 1u;
        uint32_t* const po_base = g_po + (size_t)mem * (2 * DH) + cw * (MT * 16);
        uint32_t* const pml_base = g_pml + mem * 8;

        uint32_t qa[32];
        float acc[MT][4];
        float m_run = kNegBig, l_run = 0.f;
#pragma unroll
        for (int i = 0; i < MT; i++) { acc[i][0] = acc[i][1] = acc[i][2] = acc[i][3] = 0.f; }
        int cur = -1;
        int slot = 0, ph = 0;
        {
            if (cw == 0 && lane < 2) wait_hint(&g_cnt.hint_q[(grp + 4 * lane) * 32], 32u, 100);
            __syncwarp();
            asm volatile("bar.sync 2, %0;" ::"n"(32 * W) : "memory");
            if (lane == 0 && cw == 0) TSTAMP(13);
            uint2* qs = reinterpret_cast<uint2*>(sptr + SM_QS);
#pragma unroll 1
            for (int p0 = cw * 4; p0 < PPG; p0 += 4 * W) {
                unsigned spins = 0;
                while (true) {
                    uint4 v[16];
#pragma unroll
                    for (int k = 0; k < 16; k++) {
                        const int pair = (p0 + (k >> 2)) * NG + grp;
                        v[k] = ldr4(g_q + (size_t)pair * (2 * DH) + (lane + 32 * (k & 3)) * 4);
                    }
                    uint32_t bad = 0;
#pragma unroll
                    for (int k = 0; k < 16; k++) {
                        bad |= (v[k].x ^ tag) | (v[k].y ^ tag) | (v[k].z ^ tag) | (v[k].w ^ tag);
                        qs[(p0 + (k >> 2)) * 128 + lane + 32 * (k & 3)] =
                            make_uint2(__byte_perm(v[k].x, v[k].y, 0x7632), __byte_perm(v[k].z, v[k].w, 0x7632));
                    }
                    if (__all_sync(0xffffffffu, (bad & 1u) == 0u)) break;
                    __nanosleep(100);
                    if (++spins > SPIN_LIMIT) __trap();
                }
            }
            if (lane == 0) mbar_arrive(bar_qs);
            asm volatile("bar.sync 2, %0;" ::"n"(32 * W) : "memory");
            if (lane == 0 && cw == 0) TSTAMP(2);
        }
        while (true) {
            const uint32_t fk = bar_full + (2 * slot) * 8;
            mbar_wait(fk, ph);
            const int pl = info[slot];
            if (pl != cur) {
                const int upto = (pl < 0) ? PPG : pl;
                for (int p = (cur < 0 ? 0 : cur); p < upto; p++) {
                    const int pair = p * NG + grp;
                    uint32_t* po = po_base + (size_t)pair * (GSZ * 2 * DH);
#pragma unroll
                    for (int i = 0; i < MT; i++) {
                        if ((i & 3) == t) {
                            str1(po + i * 16 + g, enc(acc[i][0], tag));
                            str1(po + DH + i * 16 + g, enc(acc[i][1], tag));
                            str1(po + i * 16 + 8 + g, enc(acc[i][2], tag));
                            str1(po + DH + i * 16 + 8 + g, enc(acc[i][3], tag));
                        }
                    }
                    float l = l_run;
                    l += __shfl_xor_sync(0xffffffffu, l, 4);
                    l += __shfl_xor_sync(0xffffffffu, l, 8);
                    l += __shfl_xor_sync(0xffffffffu, l, 16);
                    if (cw == 0 && lane < 4) {
                        const uint32_t em = enc(m_run, tag), el = enc(l, tag);
                        str4(pml_base + (pair * 2 + (lane & 1)) * (GSZ * 8) + (lane >> 1) * 4, em, el, em, el);
                    }
                    __syncwarp();
                    if (lane == 0 && p < PPG - 1) red_add(&g_cnt.hint_pair[pair * 32], 1u);
                    m_run = kNegBig; l_run = 0.f;
#pragma unroll
                    for (int i = 0; i < MT; i++) { acc[i][0] = acc[i][1] = acc[i][2] = acc[i][3] = 0.f; }
                }
                if (cw == 0 && lane == 0) *flushed = upto;
                if (pl < 0) break;
                cur = pl;
                const uint4* qp = reinterpret_cast<const uint4*>(sptr + SM_QS) + ((pl * 2 + (g & 1)) * 4 + t) * 8;
#pragma unroll
                for (int i = 0; i < 8; i++) {
                    const uint4 v = qp[i];
                    qa[4 * i] = v.x; qa[4 * i + 1] = v.y; qa[4 * i + 2] = v.z; qa[4 * i + 3] = v.w;
                }
            }
            const uint32_t kb = sbase + SM_RING + (2 * slot) * HS_BYTES;
            const uint32_t vb = kb + HS_BYTES;
            float s[2][2][4];
#pragma unroll
            for (int m = 0; m < 2; m++)
#pragma unroll
                for (int e = 0; e < 2; e++) { s[m][e][0] = s[m][e][1] = s[m][e][2] = s[m][e][3] = 0.f; }
            uint32_t kf[2][4][4];
#pragma unroll
            for (int u = 0; u < 4; u++)
                ldsm_x4(kb + (u & 1) * 2048 + (koff ^ ((u >> 1) << 5)), kf[0][u][0], kf[0][u][1], kf[0][u][2], kf[0][u][3]);
#pragma unroll
            for (int j2 = 0; j2 < 8; j2++) {
                if (j2 < 7) {
#pragma unroll
                    for (int u = 0; u < 4; u++) {
                        const int ks = 2 * (j2 + 1) + (u >> 1);
                        ldsm_x4(kb + (ks >> 2) * 4096 + (u & 1) * 2048 + (koff ^ ((ks & 3) << 5)),
                                kf[(j2 + 1) & 1][u][0], kf[(j2 + 1) & 1][u][1], kf[(j2 + 1) & 1][u][2], kf[(j2 + 1) & 1][u][3]);
                    }
                }
#pragma unroll
                for (int u = 0; u < 4; u++) {
                    const int ks = 2 * j2 + (u >> 1);
                    mma_bf16(s[u & 1][u >> 1], kf[j2 & 1][u][0], kf[j2 & 1][u][1], kf[j2 & 1][u][2], kf[j2 & 1][u][3],
                             qa[2 * ks], qa[2 * ks + 1]);
                }
            }
            mbar_wait(fk + 8, ph);
            constexpr int NGRP = 2 * MT / 4;
            uint32_t vf[2][4][4];
#pragma unroll
            for (int i = 0; i < 4; i++)
                ldsm_x4_t(vb + ((cw * MT + i) >> 2) * 4096 + (voff ^ (i << 5)), vf[0][i][0], vf[0][i][1], vf[0][i][2], vf[0][i][3]);
            float sv[2][2];
#pragma unroll
            for (int m = 0; m < 2; m++) {
                const float lo = (t & 1) ? s[m][0][1] + s[m][1][1] : s[m][0][0] + s[m][1][0];
                const float hi = (t & 1) ? s[m][0][3] + s[m][1][3] : s[m][0][2] + s[m][1][2];
                const uint32_t pk = pack_bf16(lo, hi);
                sv[m][0] = bf_lo(pk) * kQKScaleLog2;
                sv[m][1] = bf_hi(pk) * kQKScaleLog2;
            }
            if (lane == 0) mbar_arrive(bar_empty + (2 * slot) * 8 + never(sv[0][0] + sv[0][1] + sv[1][0] + sv[1][1]));
            float mx = fmaxf(fmaxf(sv[0][0], sv[0][1]), fmaxf(sv[1][0], sv[1][1]));
            if (__any_sync(0xffffffffu, mx > m_run)) {
                mx = fmaxf(mx, __shfl_xor_sync(0xffffffffu, mx, 4));
                mx = fmaxf(mx, __shfl_xor_sync(0xffffffffu, mx, 8));
                mx = fmaxf(mx, __shfl_xor_sync(0xffffffffu, mx, 16));
                const float m_new = fmaxf(m_run, mx);
                const float f = ex2f(m_run - m_new);
                const float fo = __shfl_xor_sync(0xffffffffu, f, 1);
                const float f0 = (t & 1) ? fo : f, f1 = (t & 1) ? f : fo;
                m_run = m_new;
                l_run *= f;
#pragma unroll
                for (int i = 0; i < MT; i++) {
                    acc[i][0] *= f0; acc[i][1] *= f1; acc[i][2] *= f0; acc[i][3] *= f1;
                }
            }
            uint32_t pb[4];
#pragma unroll
            for (int m = 0; m < 2; m++) {
                const float p0 = ex2f(sv[m][0] - m_run), p1 = ex2f(sv[m][1] - m_run);
                l_run += p0 + p1;
                const uint32_t pk = pack_bf16(p0, p1);
                pb[2 * m] = __shfl_sync(0xffffffffu, pk, psrc);
                pb[2 * m + 1] = __shfl_sync(0xffffffffu, pk, psrc + 16);
            }
#pragma unroll
            for (int gi = 0; gi < NGRP; gi++) {
                if (gi + 1 < NGRP) {
                    const int kk = (gi + 1) / (MT / 4), i0 = ((gi + 1) % (MT / 4)) * 4;
#pragma unroll
                    for (int i = 0; i < 4; i++)
                        ldsm_x4_t(vb + ((cw * MT + i0 + i) >> 2) * 4096 + kk * 2048 + (voff ^ (i << 5)),
                                  vf[(gi + 1) & 1][i][0], vf[(gi + 1) & 1][i][1], vf[(gi + 1) & 1][i][2], vf[(gi + 1) & 1][i][3]);
                }
                const int kk = gi / (MT / 4), i0 = (gi % (MT / 4)) * 4;
#pragma unroll
                for (int i = 0; i < 4; i++)
                    mma_bf16(acc[i0 + i], vf[gi & 1][i][0], vf[gi & 1][i][1], vf[gi & 1][i][2], vf[gi & 1][i][3],
                             pb[2 * kk], pb[2 * kk + 1]);
            }
            {
                float dsum = 0.f;
#pragma unroll
                for (int i = 0; i < MT; i++) dsum += acc[i][0];
                if (lane == 0) mbar_arrive(bar_empty + (2 * slot + 1) * 8 + never(dsum));
            }
            if (++slot == NITEM) { slot = 0; ph ^= 1; }
        }
        if (lane == 0 && cw == 0) TSTAMP(3);
    } else if (cta >= S2_CTAS) {
        mbar_arrive(bar_wq);
    } else {
        const int st = tid - 32 * (W + 1);
        const int sw = st >> 5;
        const int g = lane >> 2, t = lane & 3;
        float* misc = reinterpret_cast<float*>(sptr + SM_MISC);
        if (st == 0) TSTAMP(12);
        const uint32_t tag = (epoch + 1u) & 1u;

        {
            __nv_bfloat16* xs = reinterpret_cast<__nv_bfloat16*>(sptr + SM_WO);
            __nv_bfloat16* xraw = reinterpret_cast<__nv_bfloat16*>(sptr + SM_MISC + 4096);
#pragma unroll
            for (int bb = 0; bb < 2; bb++) {
                const int b = 2 * sw + bb;
#pragma unroll
                for (int i = 0; i < 14; i++) xraw[b * DM + i * 32 + lane] = __float2bfloat16_rn(xv[bb][i]);
                warp_layernorm14(xv[bb]);
#pragma unroll
                for (int i = 0; i < 14; i++) xs[b * XS_PITCH + i * 32 + lane] = __float2bfloat16_rn(xv[bb][i]);
            }
            if (st == 0) TSTAMP(10);
            cp_async_wait_all();
            if (st == 0) TSTAMP(11);
            serv_sync();
            float qc0[4] = {0.f, 0.f, 0.f, 0.f}, qc1[4] = {0.f, 0.f, 0.f, 0.f};
            const uint32_t* xw = reinterpret_cast<const uint32_t*>(xs) + g * (XS_PITCH / 2) + t;
            const int kr = lane;
            const uint32_t wbase = sbase + SM_WQ + kr * 64 + ((sw ^ ((kr >> 1) & 3)) << 4);
#pragma unroll
            for (int k32 = 0; k32 < 14; k32++) {
                uint32_t b0, b1r, b2r, b3;
                ldsm_x4_t(wbase + k32 * 2048, b0, b1r, b2r, b3);
                const uint32_t a0 = xw[k32 * 16], a1 = xw[k32 * 16 + 4], a2 = xw[k32 * 16 + 8], a3 = xw[k32 * 16 + 12];
                mma_bf16(qc0, a0, 0u, a1, 0u, b0, b1r);
                mma_bf16(qc1, a2, 0u, a3, 0u, b2r, b3);
            }
            *reinterpret_cast<uint2*>(misc + (g * 4 + t) * 8 + sw * 2) =
                make_uint2(enc(bf16r(qc0[0] + qc1[0]), tag), enc(bf16r(qc0[1] + qc1[1]), tag));
            asm volatile("fence.proxy.async.shared::cta;" ::: "memory");
            mbar_arrive(bar_wq);
            serv_sync();
            if (st < 64) {
                const int bt = st >> 1;
                const uint4 v = *reinterpret_cast<const uint4*>(misc + st * 4);
                const int qi = (((bt >> 2) * HQ + (cta >> 3)) * 4 + (bt & 3)) * 64 + (cta & 7) * 8 + (st & 1) * 4;
                str4(g_q + qi, v.x, v.y, v.z, v.w);
                __syncwarp();
                if (lane == 0) red_add(&g_cnt.hint_q[(cta >> 4) * 32], 1u);
            }
            if (st == 0) TSTAMP(4);
        }

        const int s2_i = cta >> 3, s2_j = cta & 7;
        mbar_wait(bar_qs, 0);
        {
            const __nv_bfloat16* src = wo + (size_t)(s2_i * DH) * DM + s2_j * S2_COLS;
#pragma unroll
            for (int k = 0; k < 14; k++) {
                const int c = st + k * 128;
                const int r = c / 7, cc = c - r * 7;
                cp_async16(sbase + SM_WO + c * 16, src + (size_t)r * DM + cc * 8);
            }
        }
        float pw1[14], pb1[14], pw2[14];
#pragma unroll
        for (int k = 0; k < 7; k++) {
            const int f2 = st + k * 128;
            const uint32_t a = __ldg(reinterpret_cast<const uint32_t*>(w1) + f2);
            const uint32_t bq = __ldg(reinterpret_cast<const uint32_t*>(b1) + f2);
            const uint32_t c = __ldg(reinterpret_cast<const uint32_t*>(w2) + f2);
            pw1[2 * k] = bf_lo(a); pw1[2 * k + 1] = bf_hi(a);
            pb1[2 * k] = bf_lo(bq); pb1[2 * k + 1] = bf_hi(bq);
            pw2[2 * k] = bf_lo(c); pw2[2 * k + 1] = bf_hi(c);
        }
        float linA = 0.f, linB = 0.f;
#pragma unroll
        for (int k = 0; k < 14; k++) {
            pw2[k] *= 0.5f;
            linA = fmaf(pw2[k], pw1[k], linA);
            linB = fmaf(pw2[k], pb1[k], linB);
        }
        const float b2v = __bfloat162float(b2[0]);
        cp_async_wait_all();
        serv_sync();

        uint32_t* o_sb = reinterpret_cast<uint32_t*>(misc);
        float* wts = misc + 256;
        float* h_s = misc + 512;
        float* red = misc + 960;

        for (int b = 0; b < NB; b++) {
            {
                const int pair = b * HKV + (s2_i >> 1), hh = s2_i & 1;
                if (st == 0) {
                    if (pair / NG < PPG - 1) wait_hint(&g_cnt.hint_pair[pair * 32], (unsigned)(GSZ * W), 200);
                    else {
                        unsigned spins = 0;
                        while (*flushed < PPG) { __nanosleep(20); if (++spins > SPIN_LIMIT) __trap(); }
                    }
                }
                serv_sync();
                if (b == NB - 1 && st == 0) TSTAMP(5);
                static_assert(GSZ == 33, "combine assumes 32 + 1 slots");
                uint32_t af[16][4];
                const uint32_t wa0 = sbase + SM_WO + ((lane >> 4) * 8 + (lane & 7)) * (S2_COLS * 2) + sw * 32 + ((lane >> 3) & 1) * 16;
                const uint32_t* mlp = g_pml + (pair * 2 + hh) * (GSZ * 8);
                const uint32_t* op = g_po + ((size_t)(pair * GSZ) * 2 + hh) * DH + 2 * st;
                const uint32_t stale = tag ^ 1u;
                uint2 ov[GSZ];
#pragma unroll
                for (int s = 0; s < GSZ; s++) ov[s] = make_uint2(stale, stale);
                uint2 mla = make_uint2(stale, stale), mlb = make_uint2(stale, stale);
                unsigned spins = 0;
                while (true) {
                    ldr2_if(mla, mlp + lane * 8, ((mla.x ^ tag) | (mla.y ^ tag)) & 1u);
                    ldr2_if(mlb, mlp + 256, ((mlb.x ^ tag) | (mlb.y ^ tag)) & 1u);
#pragma unroll
                    for (int s = 0; s < GSZ; s++)
                        ldr2_if(ov[s], op + s * (2 * DH), ((ov[s].x ^ tag) | (ov[s].y ^ tag)) & 1u);
                    uint32_t bad = (mla.x ^ tag) | (mla.y ^ tag) | (mlb.x ^ tag) | (mlb.y ^ tag);
#pragma unroll
                    for (int s = 0; s < GSZ; s++) bad |= (ov[s].x ^ tag) | (ov[s].y ^ tag);
                    if (__all_sync(0xffffffffu, (bad & 1u) == 0u)) break;
                    __nanosleep(20);
                    if (++spins > SPIN_LIMIT) __trap();
                }
                if (b == NB - 1 && st == 0) TSTAMP(14);
                const float ma = dec(mla.x), la = dec(mla.y), mb_ = dec(mlb.x), lb = dec(mlb.y);
                const float M = fmaxf(warp_max(ma), mb_);
                const float wa_ = ex2f(ma - M), wb_ = ex2f(mb_ - M);
                float* wsm = wts + sw * 64;
                wsm[lane] = wa_;
                wsm[32 + lane] = wa_ * la;
                __syncwarp();
                float o0 = wb_ * dec(ov[32].x), o1 = wb_ * dec(ov[32].y), o2 = 0.f, o3 = 0.f;
                float L0 = wb_ * lb, L1 = 0.f;
#pragma unroll
                for (int s4 = 0; s4 < 8; s4++) {
                    const float4 w4 = *reinterpret_cast<const float4*>(wsm + 4 * s4);
                    const float4 l4 = *reinterpret_cast<const float4*>(wsm + 32 + 4 * s4);
                    o0 = fmaf(w4.x, dec(ov[4 * s4].x), o0);     o1 = fmaf(w4.x, dec(ov[4 * s4].y), o1);
                    o2 = fmaf(w4.y, dec(ov[4 * s4 + 1].x), o2); o3 = fmaf(w4.y, dec(ov[4 * s4 + 1].y), o3);
                    o0 = fmaf(w4.z, dec(ov[4 * s4 + 2].x), o0); o1 = fmaf(w4.z, dec(ov[4 * s4 + 2].y), o1);
                    o2 = fmaf(w4.w, dec(ov[4 * s4 + 3].x), o2); o3 = fmaf(w4.w, dec(ov[4 * s4 + 3].y), o3);
                    L0 += l4.x + l4.y; L1 += l4.z + l4.w;
                }
                const float inv = rcp_fast(L0 + L1);
                o_sb[(st & 3) * 36 + (st >> 2)] = pack_bf16((o0 + o2) * inv, (o1 + o3) * inv);
                {
#pragma unroll
                    for (int ks = 0; ks < 16; ks++)
                        ldsm_x4_t(wa0 + ks * 16 * (S2_COLS * 2), af[ks][0], af[ks][1], af[ks][2], af[ks][3]);
                    serv_sync();
                    float d0[4] = {0.f, 0.f, 0.f, 0.f}, d1[4] = {0.f, 0.f, 0.f, 0.f};
                    float d2[4] = {0.f, 0.f, 0.f, 0.f}, d3[4] = {0.f, 0.f, 0.f, 0.f};
#pragma unroll
                    for (int k4 = 0; k4 < 4; k4++) {
                        const uint4 bw = *reinterpret_cast<const uint4*>(o_sb + t * 36 + 8 * k4);
                        const uint4 bx = *reinterpret_cast<const uint4*>(o_sb + t * 36 + 8 * k4 + 4);
                        mma_bf16(d0, af[4 * k4][0], af[4 * k4][1], af[4 * k4][2], af[4 * k4][3], bw.x, bw.y);
                        mma_bf16(d1, af[4 * k4 + 1][0], af[4 * k4 + 1][1], af[4 * k4 + 1][2], af[4 * k4 + 1][3], bw.z, bw.w);
                        mma_bf16(d2, af[4 * k4 + 2][0], af[4 * k4 + 2][1], af[4 * k4 + 2][2], af[4 * k4 + 2][3], bx.x, bx.y);
                        mma_bf16(d3, af[4 * k4 + 3][0], af[4 * k4 + 3][1], af[4 * k4 + 3][2], af[4 * k4 + 3][3], bx.z, bx.w);
                    }
                    d0[0] += d2[0]; d0[2] += d2[2]; d1[0] += d3[0]; d1[2] += d3[2];
                    const int col = sw * 16 + t * 8 + g;
                    if (t < 2 && col < S2_COLS) {
                        const float v = t ? d0[2] + d1[2] : d0[0] + d1[0];
                        str1(g_hp + (b * HQ + s2_i) * DM + s2_j * S2_COLS + col, enc(v, tag));
                    }
                }
                __syncwarp();
                if (lane == 0 && b < NB - 1) red_add(&g_cnt.hint_batch[b * 32], 1u);
                if (b == NB - 1 && st == 0) TSTAMP(6);
            }
            if (cta < S3_CTAS) {
                if (st == 0) {
                    if (b < NB - 1) wait_hint(&g_cnt.hint_batch[b * 32], 4u * S2_CTAS, 200);
                    else {
                        unsigned spins = 0;
                        while (*flushed < PPG) { __nanosleep(20); if (++spins > SPIN_LIMIT) __trap(); }
                    }
                }
                serv_sync();
                if (st < 112) {
                    const uint32_t* hp = g_hp + (size_t)b * HQ * DM + 4 * st;
                    const uint2 xw = *(reinterpret_cast<const uint2*>(sptr + SM_MISC + 4096 + b * DM * 2) + st);
                    const uint32_t stale = tag ^ 1u;
                    uint4 pv[16];
#pragma unroll
                    for (int i = 0; i < 16; i++) pv[i] = make_uint4(stale, stale, stale, stale);
                    unsigned spins = 0;
                    while (true) {
#pragma unroll
                        for (int i = 0; i < 16; i++)
                            ldr4_if(pv[i], hp + i * DM,
                                    ((pv[i].x ^ tag) | (pv[i].y ^ tag) | (pv[i].z ^ tag) | (pv[i].w ^ tag)) & 1u);
                        uint32_t bad = 0;
#pragma unroll
                        for (int i = 0; i < 16; i++)
                            bad |= (pv[i].x ^ tag) | (pv[i].y ^ tag) | (pv[i].z ^ tag) | (pv[i].w ^ tag);
                        if ((bad & 1u) == 0u) break;
                        __nanosleep(20);
                        if (++spins > SPIN_LIMIT) __trap();
                    }
                    float a0 = 0.f, a1 = 0.f, a2 = 0.f, a3 = 0.f;
#pragma unroll
                    for (int i = 0; i < 16; i++) {
                        a0 += dec(pv[i].x); a1 += dec(pv[i].y); a2 += dec(pv[i].z); a3 += dec(pv[i].w);
                    }
                    bf16r2(a0, a1); bf16r2(a2, a3);
                    a0 += bf_lo(xw.x); a1 += bf_hi(xw.x); a2 += bf_lo(xw.y); a3 += bf_hi(xw.y);
                    bf16r2(a0, a1); bf16r2(a2, a3);
                    *reinterpret_cast<float4*>(h_s + 4 * st) = make_float4(a0, a1, a2, a3);
                }
                serv_sync();
                if (b == NB - 1 && st == 0) TSTAMP(7);
                float v[14];
#pragma unroll
                for (int i = 0; i < 14; i++) v[i] = h_s[i * 32 + lane];
                warp_layernorm14(v);
                warp_layernorm14(v);
                const int c0 = 4 * cta;
                float sel = 0.f;
#pragma unroll
                for (int i = 0; i < 14; i++) if (i == (c0 >> 5)) sel = v[i];
                float tt[4];
#pragma unroll
                for (int c = 0; c < 4; c++) tt[c] = __shfl_sync(0xffffffffu, sel, (c0 & 31) + c);
                if (b == NB - 1 && st == 0) TSTAMP(15);
                float ya[4];
#pragma unroll
                for (int c = 0; c < 4; c++) ya[c] = fmaf(tt[c], linA, linB);
#pragma unroll
                for (int k = 0; k < 14; k++) {
#pragma unroll
                    for (int c = 0; c < 4; c++) {
                        const float u = fmaf(tt[c], pw1[k], pb1[k]);
                        const float z = u * fmaf(u * u, 0.7978845608028654f * 0.044715f, 0.7978845608028654f);
                        ya[c] = fmaf(pw2[k] * u, tanh_fast(z), ya[c]);
                    }
                }
#pragma unroll
                for (int o = 16; o > 0; o >>= 1) {
#pragma unroll
                    for (int c = 0; c < 4; c++) ya[c] += __shfl_xor_sync(0xffffffffu, ya[c], o);
                }
                if (lane == 0) *reinterpret_cast<float4*>(red + sw * 4) = make_float4(ya[0], ya[1], ya[2], ya[3]);
                serv_sync();
                if (st < 4) {
                    const float y = (red[st] + red[4 + st]) + (red[8 + st] + red[12 + st]);
                    const float y2 = bf16r(bf16r(y) + b2v);
                    out[b * DM + c0 + st] = __float2bfloat16_rn(h_s[c0 + st] + y2);
                }
            }
        }
        if (st == 0) TSTAMP(8);
        if (cta == 0) {
            if (st < NG) g_cnt.ticket[st] = 0u;
            if (st < HKV) g_cnt.hint_q[st * 32] = 0u;
            if (st < NB * HKV) g_cnt.hint_pair[st * 32] = 0u;
            if (st < NB) g_cnt.hint_batch[st * 32] = 0u;
            if (st == 0) g_cnt.epoch[0] = epoch + 1u;
        }
    }
}

constexpr int FB_SPLIT = 32, FB_KEYS = SK / FB_SPLIT;
__device__ float f_q[NB * HQ * DH];
__device__ float f_po[NB * HKV * FB_SPLIT * 2 * DH];
__device__ float2 f_ml[NB * HKV * FB_SPLIT * 2];
__device__ float f_hp[NB * HQ * DM];

__global__ void fb_q_kernel(const __nv_bfloat16* __restrict__ x, const __nv_bfloat16* __restrict__ wq) {
    __shared__ float xs[NB][DM];
    const int warp = threadIdx.x >> 5, lane = threadIdx.x & 31;
    float v[14];
#pragma unroll
    for (int i = 0; i < 14; i++) v[i] = __bfloat162float(x[warp * DM + i * 32 + lane]);
    warp_layernorm14(v);
#pragma unroll
    for (int i = 0; i < 14; i++) xs[warp][i * 32 + lane] = v[i];
    __syncthreads();
    const int col = blockIdx.x * 32 + lane;
    float acc = 0.f;
    for (int k = 0; k < DM; k++) acc = fmaf(xs[warp][k], __bfloat162float(wq[(size_t)k * (HQ * DH) + col]), acc);
    f_q[warp * (HQ * DH) + col] = bf16r(acc);
}
__global__ void fb_attn_kernel(const __nv_bfloat16* __restrict__ kc, const __nv_bfloat16* __restrict__ vc) {
    __shared__ float q_s[2][DH], sc[2][FB_KEYS], mx[2], ls[2];
    const int pair = blockIdx.x / FB_SPLIT, split = blockIdx.x % FB_SPLIT;
    const int tid = threadIdx.x, warp = tid >> 5, lane = tid & 31;
    q_s[0][tid] = f_q[pair * 2 * DH + tid];
    q_s[1][tid] = f_q[pair * 2 * DH + DH + tid];
    __syncthreads();
    const size_t row0 = (size_t)pair * SK + split * FB_KEYS;
    for (int k = warp; k < FB_KEYS; k += 8) {
        float a0 = 0.f, a1 = 0.f;
        for (int d = lane; d < DH; d += 32) {
            const float kv = __bfloat162float(kc[(row0 + k) * DH + d]);
            a0 = fmaf(kv, q_s[0][d], a0); a1 = fmaf(kv, q_s[1][d], a1);
        }
        a0 = warp_sum(a0); a1 = warp_sum(a1);
        if (lane == 0) { sc[0][k] = bf16r(a0) * kQKScaleLog2; sc[1][k] = bf16r(a1) * kQKScaleLog2; }
    }
    __syncthreads();
    if (warp < 2) {
        float m = kNegBig;
        for (int k = lane; k < FB_KEYS; k += 32) m = fmaxf(m, sc[warp][k]);
        m = warp_max(m);
        float l = 0.f;
        for (int k = lane; k < FB_KEYS; k += 32) { const float pp = ex2f(sc[warp][k] - m); l += pp; sc[warp][k] = bf16r(pp); }
        l = warp_sum(l);
        if (lane == 0) { mx[warp] = m; ls[warp] = l; }
    }
    __syncthreads();
    float o0 = 0.f, o1 = 0.f;
    for (int k = 0; k < FB_KEYS; k++) {
        const float vv = __bfloat162float(vc[(row0 + k) * DH + tid]);
        o0 = fmaf(sc[0][k], vv, o0); o1 = fmaf(sc[1][k], vv, o1);
    }
    f_po[(size_t)(blockIdx.x * 2) * DH + tid] = o0;
    f_po[(size_t)(blockIdx.x * 2 + 1) * DH + tid] = o1;
    if (tid < 2) f_ml[blockIdx.x * 2 + tid] = make_float2(mx[tid], ls[tid]);
}
__global__ void fb_wo_kernel(const __nv_bfloat16* __restrict__ wo) {
    __shared__ float o_s[DH];
    const int b = blockIdx.x / HQ, qh = blockIdx.x % HQ, tid = threadIdx.x;
    const int pair = b * HKV + (qh >> 1), hh = qh & 1;
    float M = kNegBig;
    for (int s = 0; s < FB_SPLIT; s++) M = fmaxf(M, f_ml[(pair * FB_SPLIT + s) * 2 + hh].x);
    float L = 0.f, o = 0.f;
    for (int s = 0; s < FB_SPLIT; s++) {
        const float2 ml = f_ml[(pair * FB_SPLIT + s) * 2 + hh];
        const float w = ex2f(ml.x - M);
        L = fmaf(w, ml.y, L);
        o = fmaf(w, f_po[(size_t)((pair * FB_SPLIT + s) * 2 + hh) * DH + tid], o);
    }
    o_s[tid] = bf16r(o / L);
    __syncthreads();
    for (int c = tid; c < DM; c += 256) {
        float a = 0.f;
        for (int d = 0; d < DH; d++) a = fmaf(o_s[d], __bfloat162float(wo[(size_t)(qh * DH + d) * DM + c]), a);
        f_hp[(b * HQ + qh) * DM + c] = a;
    }
}
__global__ void fb_mlp_kernel(const __nv_bfloat16* __restrict__ x, const __nv_bfloat16* __restrict__ w1,
                              const __nv_bfloat16* __restrict__ b1, const __nv_bfloat16* __restrict__ w2,
                              const __nv_bfloat16* __restrict__ b2, __nv_bfloat16* __restrict__ out) {
    const int b = blockIdx.x / (DM / 8), col = (blockIdx.x % (DM / 8)) * 8 + (threadIdx.x >> 5), lane = threadIdx.x & 31;
    float v[14], h[14];
#pragma unroll
    for (int i = 0; i < 14; i++) {
        const int c = i * 32 + lane;
        float a = 0.f;
        for (int q = 0; q < HQ; q++) a += f_hp[(b * HQ + q) * DM + c];
        h[i] = v[i] = bf16r(__bfloat162float(x[b * DM + c]) + bf16r(a));
    }
    warp_layernorm14(v);
    warp_layernorm14(v);
    float tsel = 0.f, hsel = 0.f;
#pragma unroll
    for (int i = 0; i < 14; i++) if (i == (col >> 5)) { tsel = v[i]; hsel = h[i]; }
    const float tt = __shfl_sync(0xffffffffu, tsel, col & 31), hv = __shfl_sync(0xffffffffu, hsel, col & 31);
    float y = 0.f;
    for (int f = lane; f < 1792; f += 32) {
        const float u = fmaf(tt, __bfloat162float(w1[f]), __bfloat162float(b1[f]));
        const float z = u * fmaf(u * u, 0.7978845608028654f * 0.044715f, 0.7978845608028654f);
        y = fmaf(0.5f * u * (1.f + tanhf(z)), __bfloat162float(w2[f]), y);
    }
    y = warp_sum(y);
    if (lane == 0) out[b * DM + col] = __float2bfloat16_rn(hv + bf16r(bf16r(y) + __bfloat162float(b2[0])));
}

typedef CUresult (*EncodeTiledFn)(CUtensorMap*, CUtensorMapDataType, cuuint32_t, void*, const cuuint64_t*,
                                  const cuuint64_t*, const cuuint32_t*, const cuuint32_t*, CUtensorMapInterleave,
                                  CUtensorMapSwizzle, CUtensorMapL2promotion, CUtensorMapFloatOOBfill);

}

extern "C" void kernel_launch(void* const* d_in, const int* in_sizes, int n_in, void* d_out, int out_size) {
    (void)in_sizes; (void)n_in; (void)out_size;
    const __nv_bfloat16* x = (const __nv_bfloat16*)d_in[0];
    const __nv_bfloat16* wq = (const __nv_bfloat16*)d_in[3];
    const __nv_bfloat16* wo = (const __nv_bfloat16*)d_in[4];
    const __nv_bfloat16* w1 = (const __nv_bfloat16*)d_in[6];
    const __nv_bfloat16* b1 = (const __nv_bfloat16*)d_in[7];
    const __nv_bfloat16* w2 = (const __nv_bfloat16*)d_in[8];
    const __nv_bfloat16* b2 = (const __nv_bfloat16*)d_in[9];

    static int mode = -1;
    static EncodeTiledFn enc_fn = nullptr;
    if (mode < 0) {
        void* fn = nullptr;
        cudaDriverEntryPointQueryResult qr;
        cudaGetDriverEntryPoint("cuTensorMapEncodeTiled", &fn, cudaEnableDefault, &qr);
        enc_fn = (EncodeTiledFn)fn;
        int dev = 0, sms = 0, occ = 0;
        cudaGetDevice(&dev);
        cudaDeviceGetAttribute(&sms, cudaDevAttrMultiProcessorCount, dev);
        const cudaError_t e1 =
            cudaFuncSetAttribute(fused_decode_kernel, cudaFuncAttributeMaxDynamicSharedMemorySize, SM_TOTAL);
        const cudaError_t e2 = cudaOccupancyMaxActiveBlocksPerMultiprocessor(&occ, fused_decode_kernel, NTHREADS, SM_TOTAL);
        mode = (enc_fn && e1 == cudaSuccess && e2 == cudaSuccess && occ * sms >= NCTA) ? 1 : 0;
        (void)cudaGetLastError();
    }
    if (mode == 1) {
        CUtensorMap tmk, tmv;
        const cuuint64_t gd[3] = {64, (cuuint64_t)NB * HKV * SK, 4};
        const cuuint64_t gs[2] = {512, 128};
        const cuuint32_t bd[3] = {64, TILE, 4};
        const cuuint32_t es[3] = {1, 1, 1};
        const CUresult r1 = enc_fn(&tmk, CU_TENSOR_MAP_DATA_TYPE_BFLOAT16, 3, d_in[1], gd, gs, bd, es,
                                   CU_TENSOR_MAP_INTERLEAVE_NONE, CU_TENSOR_MAP_SWIZZLE_128B,
                                   CU_TENSOR_MAP_L2_PROMOTION_L2_256B, CU_TENSOR_MAP_FLOAT_OOB_FILL_NONE);
        const CUresult r2 = enc_fn(&tmv, CU_TENSOR_MAP_DATA_TYPE_BFLOAT16, 3, d_in[2], gd, gs, bd, es,
                                   CU_TENSOR_MAP_INTERLEAVE_NONE, CU_TENSOR_MAP_SWIZZLE_128B,
                                   CU_TENSOR_MAP_L2_PROMOTION_L2_256B, CU_TENSOR_MAP_FLOAT_OOB_FILL_NONE);
        if (r1 == CUDA_SUCCESS && r2 == CUDA_SUCCESS) {
            cudaLaunchConfig_t cfg = {};
            cfg.gridDim = dim3(NCTA);
            cfg.blockDim = dim3(NTHREADS);
            cfg.dynamicSmemBytes = SM_TOTAL;
            cfg.stream = 0;
            cudaLaunchAttribute at[1];
            at[0].id = cudaLaunchAttributeCooperative;
            at[0].val.cooperative = 1;
            cfg.attrs = at;
            cfg.numAttrs = 1;
            if (cudaLaunchKernelEx(&cfg, fused_decode_kernel, tmk, tmv, x, wq, wo, w1, b1, w2, b2,
                                   (__nv_bfloat16*)d_out) == cudaSuccess)
                return;
            (void)cudaGetLastError();
        }
    }
    fb_q_kernel<<<HQ * DH / 32, 256>>>(x, wq);
    fb_attn_kernel<<<NB * HKV * FB_SPLIT, 256>>>((const __nv_bfloat16*)d_in[1], (const __nv_bfloat16*)d_in[2]);
    fb_wo_kernel<<<NB * HQ, 256>>>(wo);
    fb_mlp_kernel<<<NB * (DM / 8), 256>>>(x, w1, b1, w2, b2, (__nv_bfloat16*)d_out);
}
```
